```python
import torch

def _softmax(x, axis=-1):
    return torch.softmax(x, dim=axis)
def _gelu(x):
    return torch.nn.functional.gelu(x, approximate="tanh")
def _silu(x):
    return torch.nn.functional.silu(x)
def _sigmoid(x):
    return torch.sigmoid(x)
def _layernorm(x, axis=-1, eps=1e-5):
    m = x.mean(dim=axis, keepdim=True)
    v = x.var(dim=axis, keepdim=True, unbiased=False)
    return (x - m) / torch.sqrt(v + eps)
def _scatter_add(tgt, idx, src, axis=0):
    return tgt.clone().index_add_(axis, idx, src)
def _segment_sum(src, seg, n):
    out = torch.zeros((n,) + src.shape[1:], dtype=src.dtype)
    return out.index_add_(0, seg, src)
def _pad(x, pw):
    flat = tuple(v for pair in reversed(pw) for v in pair)
    return torch.nn.functional.pad(x, flat)

kernel_name = 'standalone__rezero__prompt'

def setup_inputs():

    _w = (lambda a: (lambda t: t.to(torch.bfloat16) if t.is_floating_point() else t)(torch.as_tensor(a)))
    B, S, D = 4, 2048, 448
    return {
        "x": _w((lambda *s: torch.randn(*s, dtype=torch.bfloat16) * 0.05)(B, S, D)),
        "fx": _w((lambda *s: torch.randn(*s, dtype=torch.bfloat16) * 0.4)(B, S, D)),
        "alpha": _w((lambda *s: torch.randn(*s, dtype=torch.bfloat16) * 0.4)(1) * 0.1),
    }

def reference(x, fx, alpha):
    return x + alpha * fx
```

```cpp
#include <cuda_runtime.h>
#include <cuda_bf16.h>
#include <stdint.h>


static __device__ __forceinline__ uint32_t rezero2(uint32_t x, uint32_t f, __nv_bfloat162 a) {
    __nv_bfloat162 xv = *reinterpret_cast<__nv_bfloat162*>(&x);
    __nv_bfloat162 fv = *reinterpret_cast<__nv_bfloat162*>(&f);
    __nv_bfloat162 r = __hadd2_rn(xv, __hmul2_rn(a, fv));
    return *reinterpret_cast<uint32_t*>(&r);
}

static __device__ __forceinline__ uint4 rezero8(uint4 x, uint4 f, __nv_bfloat162 a) {
    uint4 r;
    r.x = rezero2(x.x, f.x, a);
    r.y = rezero2(x.y, f.y, a);
    r.z = rezero2(x.z, f.z, a);
    r.w = rezero2(x.w, f.w, a);
    return r;
}

constexpr int THREADS = 256;
constexpr int UNROLL = 2;

__global__ void __launch_bounds__(THREADS)
rezero_kernel(const uint4* __restrict__ x, const uint4* __restrict__ fx,
              const __nv_bfloat16* __restrict__ alpha, uint4* __restrict__ out, int nvec) {
    int base = blockIdx.x * (THREADS * UNROLL) + threadIdx.x;
    uint4 xv[UNROLL], fv[UNROLL];
#pragma unroll
    for (int u = 0; u < UNROLL; u++) {
        int i = base + u * THREADS;
        if (i < nvec) {
            xv[u] = __ldg(x + i);
            fv[u] = __ldg(fx + i);
        }
    }
    __nv_bfloat162 a = __bfloat162bfloat162(__ldg(alpha));
#pragma unroll
    for (int u = 0; u < UNROLL; u++) {
        int i = base + u * THREADS;
        if (i < nvec) out[i] = rezero8(xv[u], fv[u], a);
    }
}

__global__ void rezero_tail_kernel(const __nv_bfloat16* __restrict__ x, const __nv_bfloat16* __restrict__ fx,
                                   const __nv_bfloat16* __restrict__ alpha, __nv_bfloat16* __restrict__ out,
                                   int start, int n) {
    int i = start + blockIdx.x * blockDim.x + threadIdx.x;
    if (i < n) out[i] = __hadd_rn(x[i], __hmul_rn(alpha[0], fx[i]));
}

extern "C" void kernel_launch(void* const* d_in, const int* in_sizes, int n_in,
                              void* d_out, int out_size) {
    const __nv_bfloat16* x = (const __nv_bfloat16*)d_in[0];
    const __nv_bfloat16* fx = (const __nv_bfloat16*)d_in[1];
    const __nv_bfloat16* alpha = (const __nv_bfloat16*)d_in[2];
    __nv_bfloat16* out = (__nv_bfloat16*)d_out;
    int n = out_size;
    int nvec = n / 8;
    int per_block = THREADS * UNROLL;
    int blocks = (nvec + per_block - 1) / per_block;
    if (blocks > 0)
        rezero_kernel<<<blocks, THREADS>>>((const uint4*)x, (const uint4*)fx, alpha, (uint4*)out, nvec);
    int rem = n - nvec * 8;
    if (rem > 0)
        rezero_tail_kernel<<<1, 32>>>(x, fx, alpha, out, nvec * 8, n);
}
```

```cpp
#include <cuda_runtime.h>
#include <cuda_bf16.h>
#include <stdint.h>


namespace {

constexpr int kThreads = 704;

__device__ __forceinline__ uint4 ld_stream(const uint4* p) {
    uint4 v;
    asm volatile("ld.global.nc.v4.u32 {%0,%1,%2,%3}, [%4];"
                 : "=r"(v.x), "=r"(v.y), "=r"(v.z), "=r"(v.w) : "l"(p));
    return v;
}

__device__ __forceinline__ void st_stream(uint4* p, uint4 v) {
    asm volatile("st.global.v4.u32 [%0], {%1,%2,%3,%4};"
                 :: "l"(p), "r"(v.x), "r"(v.y), "r"(v.z), "r"(v.w) : "memory");
}

__device__ __forceinline__ uint32_t rezero2(uint32_t x, uint32_t f, __nv_bfloat162 a) {
    __nv_bfloat162 xv = *reinterpret_cast<__nv_bfloat162*>(&x);
    __nv_bfloat162 fv = *reinterpret_cast<__nv_bfloat162*>(&f);
    __nv_bfloat162 r = __hadd2_rn(xv, __hmul2_rn(a, fv));
    return *reinterpret_cast<uint32_t*>(&r);
}

__device__ __forceinline__ uint4 rezero8(uint4 x, uint4 f, __nv_bfloat162 a) {
    uint4 r;
    r.x = rezero2(x.x, f.x, a);
    r.y = rezero2(x.y, f.y, a);
    r.z = rezero2(x.z, f.z, a);
    r.w = rezero2(x.w, f.w, a);
    return r;
}

__global__ void __launch_bounds__(kThreads)
rezero_vec_kernel(const uint4* __restrict__ x, const uint4* __restrict__ fx,
                  const __nv_bfloat16* __restrict__ alpha, uint4* __restrict__ out,
                  int nvec, int stride) {
    int i = blockIdx.x * kThreads + threadIdx.x;
    uint4 xv = ld_stream(x + i);
    uint4 fv = ld_stream(fx + i);
    const __nv_bfloat162 a = __bfloat162bfloat162(__ldg(alpha));
#pragma unroll 1
    while (true) {
        st_stream(out + i, rezero8(xv, fv, a));
        i += stride;
        if (i >= nvec) break;
        xv = ld_stream(x + i);
        fv = ld_stream(fx + i);
    }
}

__global__ void rezero_scalar_kernel(const __nv_bfloat16* __restrict__ x,
                                     const __nv_bfloat16* __restrict__ fx,
                                     const __nv_bfloat16* __restrict__ alpha,
                                     __nv_bfloat16* __restrict__ out, int start, int n) {
    const __nv_bfloat16 a = alpha[0];
    for (long long i = (long long)start + blockIdx.x * blockDim.x + threadIdx.x; i < n;
         i += (long long)gridDim.x * blockDim.x)
        out[i] = __hadd_rn(x[i], __hmul_rn(a, fx[i]));
}

}


#include <stdio.h>
__device__ unsigned short g_lat[132];
__global__ void probe_one(unsigned int* p) {
    extern __shared__ char pad[];
    unsigned int sm; asm volatile("mov.u32 %0, %%smid;" : "=r"(sm));
    if (threadIdx.x != 0) return;
    volatile unsigned int* sp = (volatile unsigned int*)pad;
    long long tw = clock64(); while (clock64() - tw < (long long)sm * 6000) {}
    unsigned int z = atomicAnd(p, 0xFFFFFFFFu); z = z & 0; sp[0] = z;
    unsigned int best = 0xFFFFFFFF;
    for (int k = 0; k < 3; k++) {
        long long t0 = clock64();
        unsigned int v = atomicAnd(p + z, 0xFFFFFFFFu);
        sp[1] = v;
        long long t1 = clock64();
        unsigned int d = (unsigned int)(t1 - t0);
        best = d < best ? d : best;
    }
    g_lat[sm] = (unsigned short)best;
}
static void topo(void* const* bufs) {
    cudaFuncSetAttribute(probe_one, cudaFuncAttributeMaxDynamicSharedMemorySize, 200 * 1024);
    unsigned short h[132];
    for (int b = 0; b < 3; b++) {
        fprintf(stderr, "PROBE buf %d %p: far-from-SM0 per page:", b, bufs[b]);
        for (int p = 0; p < 4; p++) {
            probe_one<<<132, 32, 200 * 1024>>>((unsigned int*)((char*)bufs[b] + (size_t)p * (2 << 20)));
            cudaDeviceSynchronize();
            cudaMemcpyFromSymbol(h, g_lat, sizeof h);
            fprintf(stderr, " %d(%d,%d)", h[0] > 400, h[0], h[2]);
        }
        fprintf(stderr, "\n");
    }
}

extern "C" void kernel_launch(void* const* d_in, const int* in_sizes, int n_in,
                              void* d_out, int out_size) {
    const __nv_bfloat16* x = (const __nv_bfloat16*)d_in[0];
    const __nv_bfloat16* fx = (const __nv_bfloat16*)d_in[1];
    const __nv_bfloat16* alpha = (const __nv_bfloat16*)d_in[2];
    __nv_bfloat16* out = (__nv_bfloat16*)d_out;
    const int n = out_size;

    static int num_sms = 0;
    if (num_sms == 0) {
        void* bufs[3] = {d_in[0], d_in[1], d_out}; topo(bufs);
        int dev = 0;
        cudaGetDevice(&dev);
        if (cudaDeviceGetAttribute(&num_sms, cudaDevAttrMultiProcessorCount, dev) != cudaSuccess ||
            num_sms <= 0)
            num_sms = 132;
    }

    const bool aligned = (((uintptr_t)x | (uintptr_t)fx | (uintptr_t)out) & 15) == 0;
    int nvec = aligned ? n / 8 : 0;
    int blocks = nvec / kThreads;
    if (blocks > num_sms) blocks = num_sms;
    if (blocks > 0) {
        rezero_vec_kernel<<<blocks, kThreads>>>((const uint4*)x, (const uint4*)fx, alpha,
                                                (uint4*)out, nvec, blocks * kThreads);
    } else {
        nvec = 0;
    }
    const int done = nvec * 8;
    if (done < n) {
        int rem = n - done;
        int sblocks = (rem + 255) / 256;
        if (sblocks > 4 * num_sms) sblocks = 4 * num_sms;
        rezero_scalar_kernel<<<sblocks, 256>>>(x, fx, alpha, out, done, n);
    }
}
```

```cpp
#include <cuda_runtime.h>
#include <cuda_bf16.h>
#include <stdint.h>


namespace {

constexpr int kThreads = 704;

__device__ __forceinline__ uint4 ld_stream(const uint4* p) {
    uint4 v;
    asm volatile("ld.global.nc.v4.u32 {%0,%1,%2,%3}, [%4];"
                 : "=r"(v.x), "=r"(v.y), "=r"(v.z), "=r"(v.w) : "l"(p));
    return v;
}

__device__ __forceinline__ void st_stream(uint4* p, uint4 v) {
    asm volatile("st.global.v4.u32 [%0], {%1,%2,%3,%4};"
                 :: "l"(p), "r"(v.x), "r"(v.y), "r"(v.z), "r"(v.w) : "memory");
}

__device__ __forceinline__ uint32_t rezero2(uint32_t x, uint32_t f, __nv_bfloat162 a) {
    __nv_bfloat162 xv = *reinterpret_cast<__nv_bfloat162*>(&x);
    __nv_bfloat162 fv = *reinterpret_cast<__nv_bfloat162*>(&f);
    __nv_bfloat162 r = __hadd2_rn(xv, __hmul2_rn(a, fv));
    return *reinterpret_cast<uint32_t*>(&r);
}

__device__ __forceinline__ uint4 rezero8(uint4 x, uint4 f, __nv_bfloat162 a) {
    uint4 r;
    r.x = rezero2(x.x, f.x, a);
    r.y = rezero2(x.y, f.y, a);
    r.z = rezero2(x.z, f.z, a);
    r.w = rezero2(x.w, f.w, a);
    return r;
}

__global__ void __launch_bounds__(kThreads)
rezero_vec_kernel(const uint4* __restrict__ x, const uint4* __restrict__ fx,
                  const __nv_bfloat16* __restrict__ alpha, uint4* __restrict__ out,
                  int nvec, int stride) {
    int i = blockIdx.x * kThreads + threadIdx.x;
    uint4 xv = ld_stream(x + i);
    uint4 fv = ld_stream(fx + i);
    const __nv_bfloat162 a = __bfloat162bfloat162(__ldg(alpha));
#pragma unroll 1
    while (true) {
        st_stream(out + i, rezero8(xv, fv, a));
        i += stride;
        if (i >= nvec) break;
        xv = ld_stream(x + i);
        fv = ld_stream(fx + i);
    }
}

__global__ void rezero_scalar_kernel(const __nv_bfloat16* __restrict__ x,
                                     const __nv_bfloat16* __restrict__ fx,
                                     const __nv_bfloat16* __restrict__ alpha,
                                     __nv_bfloat16* __restrict__ out, int start, int n) {
    const __nv_bfloat16 a = alpha[0];
    for (long long i = (long long)start + blockIdx.x * blockDim.x + threadIdx.x; i < n;
         i += (long long)gridDim.x * blockDim.x)
        out[i] = __hadd_rn(x[i], __hmul_rn(a, fx[i]));
}

}

extern "C" void kernel_launch(void* const* d_in, const int* in_sizes, int n_in,
                              void* d_out, int out_size) {
    const __nv_bfloat16* x = (const __nv_bfloat16*)d_in[0];
    const __nv_bfloat16* fx = (const __nv_bfloat16*)d_in[1];
    const __nv_bfloat16* alpha = (const __nv_bfloat16*)d_in[2];
    __nv_bfloat16* out = (__nv_bfloat16*)d_out;
    const int n = out_size;

    static int num_sms = 0;
    if (num_sms == 0) {
        int dev = 0;
        cudaGetDevice(&dev);
        if (cudaDeviceGetAttribute(&num_sms, cudaDevAttrMultiProcessorCount, dev) != cudaSuccess ||
            num_sms <= 0)
            num_sms = 132;
    }

    const bool aligned = (((uintptr_t)x | (uintptr_t)fx | (uintptr_t)out) & 15) == 0;
    int nvec = aligned ? n / 8 : 0;
    int blocks = nvec / kThreads;
    if (blocks > num_sms) blocks = num_sms;
    if (blocks > 0) {
        rezero_vec_kernel<<<blocks, kThreads>>>((const uint4*)x, (const uint4*)fx, alpha,
                                                (uint4*)out, nvec, blocks * kThreads);
    } else {
        nvec = 0;
    }
    const int done = nvec * 8;
    if (done < n) {
        int rem = n - done;
        int sblocks = (rem + 255) / 256;
        if (sblocks > 4 * num_sms) sblocks = 4 * num_sms;
        rezero_scalar_kernel<<<sblocks, 256>>>(x, fx, alpha, out, done, n);
    }
}
```
